```python
import torch

def _softmax(x, axis=-1):
    return torch.softmax(x, dim=axis)
def _gelu(x):
    return torch.nn.functional.gelu(x, approximate="tanh")
def _silu(x):
    return torch.nn.functional.silu(x)
def _sigmoid(x):
    return torch.sigmoid(x)
def _layernorm(x, axis=-1, eps=1e-5):
    m = x.mean(dim=axis, keepdim=True)
    v = x.var(dim=axis, keepdim=True, unbiased=False)
    return (x - m) / torch.sqrt(v + eps)
def _scatter_add(tgt, idx, src, axis=0):
    return tgt.clone().index_add_(axis, idx, src)
def _segment_sum(src, seg, n):
    out = torch.zeros((n,) + src.shape[1:], dtype=src.dtype)
    return out.index_add_(0, seg, src)
def _pad(x, pw):
    flat = tuple(v for pair in reversed(pw) for v in pair)
    return torch.nn.functional.pad(x, flat)

kernel_name = 'gated_mix__gqa_block_cached__glu_gated_glu__decode'

def setup_inputs():

    _w = (lambda a: (lambda t: t.to(torch.bfloat16) if t.is_floating_point() else t)(torch.as_tensor(a)))
    def _A_setup():
        B, Sq, D = 4, 1, 512
        Hq, Hkv, Sk, Dh = 32, 8, 8192, 128
        assert Hq % Hkv == 0, (Hq, Hkv)
        return {
            "x": _w((lambda *s: torch.randn(*s, dtype=torch.bfloat16) * 0.05)(B, Sq, D)),
            "k_cache": _w((lambda *s: torch.randn(*s, dtype=torch.bfloat16) * 6.4)(B, Hkv, Sk, Dh)),
            "v_cache": _w((lambda *s: torch.randn(*s, dtype=torch.bfloat16) * 3.2)(B, Hkv, Sk, Dh)),
            "wq": _w((lambda *s: torch.randn(*s, dtype=torch.bfloat16) * 6.4)(D, Hq * Dh) * (D ** -0.5)),
            "wo": _w((lambda *s: torch.randn(*s, dtype=torch.bfloat16) * 3.2)(Hq * Dh, D) * ((Hq * Dh) ** -0.5)),
        }
    _A_in = _A_setup()

    def _B_setup():
        B, S, D, F = 4, 1, 512, 1792
        return {
            "x": _w((lambda *s: torch.randn(*s, dtype=torch.bfloat16) * 0.05)(B, S, D)),
            "w_gate": _w((lambda *s: torch.randn(*s, dtype=torch.bfloat16) * 3.2)(D, F)),
            "w_up": _w((lambda *s: torch.randn(*s, dtype=torch.bfloat16) * 0.2)(D, F)),
            "w_down": _w((lambda *s: torch.randn(*s, dtype=torch.bfloat16) * 0.2)(F, D)),
        }
    _B_in = _B_setup()

    return {
        "A_x": _A_in["x"],
        "A_k_cache": _A_in["k_cache"],
        "A_v_cache": _A_in["v_cache"],
        "A_wq": _A_in["wq"],
        "A_wo": _A_in["wo"],
        "B_x": _B_in["x"],
        "B_w_gate": _B_in["w_gate"],
        "B_w_up": _B_in["w_up"],
        "B_w_down": _B_in["w_down"],
        "gate_w": _w((lambda *s: torch.randn(*s, dtype=torch.bfloat16) * 0.05)(512) * 16.0),
    }

def reference(A_x, A_k_cache, A_v_cache, A_wq, A_wo, B_x, B_w_gate, B_w_up, B_w_down, gate_w):
    def _A_ref(x, k_cache, v_cache, wq, wo):
        B, Sq, D = x.shape
        Hq, Dh = 32, 128
        Hkv = k_cache.shape[1]
        rep = Hq // Hkv
        q = (lambda x, *d: x.permute(*d))((x @ wq).reshape(B, Sq, Hq, Dh), 0, 2, 1, 3)
        k = (lambda x, n, axis: torch.repeat_interleave(x, n, dim=axis))(k_cache, rep, axis=1)
        v = (lambda x, n, axis: torch.repeat_interleave(x, n, dim=axis))(v_cache, rep, axis=1)
        scores = torch.einsum("bhqd,bhkd->bhqk", q, k) * (Dh ** -0.5)
        p = _softmax(scores, axis=-1)
        o = torch.einsum("bhqk,bhkd->bhqd", p, v)
        return (lambda x, *d: x.permute(*d))(o, 0, 2, 1, 3).reshape(B, Sq, Hq * Dh) @ wo

    def _B_ref(x, w_gate, w_up, w_down):
        g = torch.einsum("bsd,df->bsf", x, w_gate)
        u = torch.einsum("bsd,df->bsf", x, w_up)
        h = _sigmoid(g) * u
        return torch.einsum("bsf,fd->bsd", h, w_down)

    x = A_x
    g = _sigmoid((x * gate_w).sum(-1, keepdims=True))
    a = _A_ref(x, A_k_cache, A_v_cache, A_wq, A_wo)
    b = _B_ref(x, B_w_gate, B_w_up, B_w_down)
    return g * a + (1 - g) * b
```

```cpp
#include <cuda_runtime.h>
#include <cuda_bf16.h>
#include <cuda.h>
#include <stdint.h>
#include <stddef.h>

namespace {

constexpr int NB = 4, DM = 512, HQ = 32, HKV = 8, SK = 8192, DH = 128, FF = 1792;
constexpr int NATT = 128, NGLU = 4, NCTA = NATT + NGLU;
constexpr int TK = 64;
constexpr int TILE = 16384;
constexpr int NPAIR = 32;
constexpr int S = 10;
constexpr int GCAP = 6;
constexpr int NINIT = 1;
constexpr int TA = 400;
constexpr int TAU = 1180;
constexpr int WIN = 576;
constexpr int CAPMIN = 2, CAPMAX = 7;
constexpr int HOLD0 = 160, HOLD1 = 160, HOLD2 = 192;
constexpr int RET = 500;
constexpr int CD = 800, FD = 2300;
constexpr int QD = 6900;
constexpr int NTHREADS = 512;
constexpr int W_PROD = 0, W_PACE = 1, W_FIN = 2, W_ATT = 4, W_CMB = 8, W_PRJ = 12;
constexpr int GLU_S = 7, GLU_TILES = 56;

constexpr int XS_PITCH = 1040, OS_PITCH = 272, HS_PITCH = 240, QS_PITCH = 68;
constexpr int OFF_RING = 0;
constexpr int OFF_W    = S * TILE;
constexpr int OFF_XS   = OFF_W + 3 * TILE;
constexpr int OFF_OS   = OFF_XS + 4 * XS_PITCH;
constexpr int OFF_HS   = OFF_OS + 2048;
constexpr int OFF_RED  = OFF_HS + 4 * HS_PITCH;
constexpr int OFF_ML   = OFF_RED + 8192;
constexpr int OFF_QR   = OFF_OS;
constexpr int OFF_QS   = OFF_ML + 128;
constexpr int OFF_EP   = OFF_QS + 4 * QS_PITCH * 4;
constexpr int OFF_BAR  = OFF_EP + 32;
constexpr int BAR_FULL = 0, BAR_EMPTY = S, BAR_WQ = 2 * S, BAR_LATE = 2 * S + 4, BAR_WFREE = 2 * S + 7,
              BAR_ISS = 2 * S + 8, BAR_ATT = 2 * S + 9, BAR_TAIL = 2 * S + 10, BAR_KEEP = 2 * S + 11, NBAR = 2 * S + 12;
constexpr int SMEM_BYTES = OFF_BAR + NBAR * 8;
static_assert(SMEM_BYTES <= 232448, "smem");
static_assert(OFF_XS % 16 == 0 && OFF_OS % 16 == 0 && OFF_HS % 16 == 0 && OFF_RED % 16 == 0 && OFF_BAR % 8 == 0, "align");

constexpr int OBLK = 4 * DH + 32;
constexpr int QBLK = 512;
struct Scratch {
    uint32_t q[NB * HKV * QBLK];
    uint32_t o[HQ * NB * OBLK];
    uint32_t h[NB * FF];
    uint32_t a[128 * 32 * 32];
    uint32_t b[128 * 16 * 32];
    uint32_t prog[64];
    uint32_t epoch[32];
};
__device__ __align__(128) Scratch g_scratch;

struct Params {
    CUtensorMap k, v, wq, wo, wd, wg, wu;
    const __nv_bfloat16* x;
    const __nv_bfloat16* gate_w;
    __nv_bfloat16* out;
    Scratch* scr;
};

__device__ __forceinline__ void mbar_init(uint32_t bar, uint32_t cnt) {
    asm volatile("mbarrier.init.shared::cta.b64 [%0], %1;" ::"r"(bar), "r"(cnt) : "memory");
}
__device__ __forceinline__ void mbar_expect_tx(uint32_t bar, uint32_t bytes) {
    asm volatile("mbarrier.arrive.expect_tx.shared::cta.b64 _, [%0], %1;" ::"r"(bar), "r"(bytes) : "memory");
}
__device__ __forceinline__ void mbar_arrive(uint32_t bar) {
    asm volatile("mbarrier.arrive.shared::cta.b64 _, [%0];" ::"r"(bar) : "memory");
}
__device__ __forceinline__ bool mbar_test(uint32_t bar, uint32_t parity) {
    uint32_t ok;
    asm volatile("{\n.reg .pred p;\nmbarrier.test_wait.parity.shared::cta.b64 p, [%1], %2;\nselp.u32 %0, 1, 0, p;\n}"
                 : "=r"(ok) : "r"(bar), "r"(parity) : "memory");
    return ok;
}
constexpr uint32_t SPIN_LIMIT = 1u << 22;
__device__ __forceinline__ void mbar_wait(uint32_t bar, uint32_t parity) {
    asm volatile("{\n.reg .pred p;\n.reg .u32 n;\nmov.u32 n, 0;\n"
                 "W_%=:\nmbarrier.try_wait.parity.shared::cta.b64 p, [%0], %1;\n@p bra D_%=;\n"
                 "add.u32 n, n, 1;\nsetp.lt.u32 p, n, 4000000;\n@p bra W_%=;\ntrap;\nD_%=:\n}"
                 ::"r"(bar), "r"(parity) : "memory");
}
__device__ __forceinline__ bool elect_one() {
    uint32_t pred = 0;
    asm volatile("{\n.reg .b32 rx;\n.reg .pred px;\nelect.sync rx|px, 0xffffffff;\n@px mov.s32 %0, 1;\n}" : "+r"(pred));
    return pred;
}
template <class T> __device__ __forceinline__ void pin(T*& ptr) { asm volatile("" : "+l"(ptr)); }
__device__ __forceinline__ void pin(uint32_t& v) { asm volatile("" : "+r"(v)); }
__device__ __forceinline__ uint32_t clock32() { uint32_t t; asm volatile("mov.u32 %0, %%clock;" : "=r"(t)); return t; }
__device__ __forceinline__ void bar_sync(int id, int n) { asm volatile("bar.sync %0, %1;" ::"r"(id), "r"(n) : "memory"); }
__device__ __forceinline__ void bar_arrive(int id, int n) { asm volatile("bar.arrive %0, %1;" ::"r"(id), "r"(n) : "memory"); }

__device__ __forceinline__ void tma2d(uint32_t dst, const CUtensorMap* m, int c0, int c1, uint32_t bar, uint64_t pol) {
    asm volatile("cp.async.bulk.tensor.2d.shared::cluster.global.mbarrier::complete_tx::bytes.L2::cache_hint [%0], [%1, {%3, %4}], [%2], %5;"
                 ::"r"(dst), "l"(m), "r"(bar), "r"(c0), "r"(c1), "l"(pol) : "memory");
}
__device__ __forceinline__ void tma2d_nohint(uint32_t dst, const CUtensorMap* m, int c0, int c1, uint32_t bar) {
    asm volatile("cp.async.bulk.tensor.2d.shared::cluster.global.mbarrier::complete_tx::bytes [%0], [%1, {%3, %4}], [%2];"
                 ::"r"(dst), "l"(m), "r"(bar), "r"(c0), "r"(c1) : "memory");
}
__device__ __forceinline__ void tma3d(uint32_t dst, const CUtensorMap* m, int c1, uint32_t bar, uint64_t pol) {
    asm volatile("cp.async.bulk.tensor.3d.shared::cluster.global.mbarrier::complete_tx::bytes.L2::cache_hint [%0], [%1, {%4, %3, %4}], [%2], %5;"
                 ::"r"(dst), "l"(m), "r"(bar), "r"(c1), "r"(0), "l"(pol) : "memory");
}
__device__ __forceinline__ void ldsm4(uint32_t (&r)[4], uint32_t addr) {
    asm volatile("ldmatrix.sync.aligned.m8n8.x4.shared.b16 {%0,%1,%2,%3}, [%4];"
                 : "=r"(r[0]), "=r"(r[1]), "=r"(r[2]), "=r"(r[3]) : "r"(addr) : "memory");
}
__device__ __forceinline__ void ldsm4t(uint32_t (&r)[4], uint32_t addr) {
    asm volatile("ldmatrix.sync.aligned.m8n8.x4.trans.shared.b16 {%0,%1,%2,%3}, [%4];"
                 : "=r"(r[0]), "=r"(r[1]), "=r"(r[2]), "=r"(r[3]) : "r"(addr) : "memory");
}
__device__ __forceinline__ void mma16816(float (&c)[4], uint32_t a0, uint32_t a1, uint32_t a2, uint32_t a3, uint32_t b0, uint32_t b1) {
    asm("mma.sync.aligned.m16n8k16.row.col.f32.bf16.bf16.f32 {%0,%1,%2,%3}, {%4,%5,%6,%7}, {%8,%9}, {%0,%1,%2,%3};"
        : "+f"(c[0]), "+f"(c[1]), "+f"(c[2]), "+f"(c[3]) : "r"(a0), "r"(a1), "r"(a2), "r"(a3), "r"(b0), "r"(b1));
}
__device__ __forceinline__ uint32_t lds32(uint32_t a) { uint32_t v; asm volatile("ld.shared.u32 %0, [%1];" : "=r"(v) : "r"(a) : "memory"); return v; }
__device__ __forceinline__ float ldsf(uint32_t a) { float v; asm volatile("ld.shared.f32 %0, [%1];" : "=f"(v) : "r"(a) : "memory"); return v; }
__device__ __forceinline__ float4 ldsf4(uint32_t a) { float4 v; asm volatile("ld.shared.v4.f32 {%0,%1,%2,%3}, [%4];" : "=f"(v.x), "=f"(v.y), "=f"(v.z), "=f"(v.w) : "r"(a) : "memory"); return v; }
__device__ __forceinline__ uint4 lds128(uint32_t a) { uint4 v; asm volatile("ld.shared.v4.u32 {%0,%1,%2,%3}, [%4];" : "=r"(v.x), "=r"(v.y), "=r"(v.z), "=r"(v.w) : "r"(a) : "memory"); return v; }
__device__ __forceinline__ void sts32(uint32_t a, uint32_t v) { asm volatile("st.shared.u32 [%0], %1;" ::"r"(a), "r"(v) : "memory"); }
__device__ __forceinline__ void stsf(uint32_t a, float v) { asm volatile("st.shared.f32 [%0], %1;" ::"r"(a), "f"(v) : "memory"); }
__device__ __forceinline__ void stsf2(uint32_t a, float x, float y) { asm volatile("st.shared.v2.f32 [%0], {%1,%2};" ::"r"(a), "f"(x), "f"(y) : "memory"); }
__device__ __forceinline__ void sts64(uint32_t a, uint32_t x, uint32_t y) { asm volatile("st.shared.v2.u32 [%0], {%1,%2};" ::"r"(a), "r"(x), "r"(y) : "memory"); }
__device__ __forceinline__ void sts128(uint32_t a, uint4 v) { asm volatile("st.shared.v4.u32 [%0], {%1,%2,%3,%4};" ::"r"(a), "r"(v.x), "r"(v.y), "r"(v.z), "r"(v.w) : "memory"); }

__device__ __forceinline__ uint32_t ldv32(uint32_t a) { uint32_t v; asm volatile("ld.volatile.shared.u32 %0, [%1];" : "=r"(v) : "r"(a) : "memory"); return v; }
__device__ __forceinline__ uint2 ldv64(uint32_t a) { uint64_t v; asm volatile("ld.volatile.shared.u64 %0, [%1];" : "=l"(v) : "r"(a) : "memory"); return make_uint2((uint32_t)v, (uint32_t)(v >> 32)); }
__device__ __forceinline__ void stv32(uint32_t a, uint32_t v) { asm volatile("st.volatile.shared.u32 [%0], %1;" ::"r"(a), "r"(v) : "memory"); }
__device__ __forceinline__ void stv64(uint32_t a, uint32_t x, uint32_t y) { asm volatile("st.volatile.shared.u64 [%0], %1;" ::"r"(a), "l"(((uint64_t)y << 32) | x) : "memory"); }

__device__ __forceinline__ uint32_t ldr32(const void* p) { uint32_t v; asm volatile("ld.relaxed.gpu.global.u32 %0, [%1];" : "=r"(v) : "l"(p) : "memory"); return v; }
__device__ __forceinline__ void str32(void* p, uint32_t v) { asm volatile("st.relaxed.gpu.global.u32 [%0], %1;" ::"l"(p), "r"(v) : "memory"); }
__device__ __forceinline__ void str64(void* p, uint32_t x, uint32_t y) { asm volatile("st.relaxed.gpu.global.v2.u32 [%0], {%1,%2};" ::"l"(p), "r"(x), "r"(y) : "memory"); }
__device__ __forceinline__ void str128(void* p, uint4 v) { asm volatile("st.relaxed.gpu.global.v4.u32 [%0], {%1,%2,%3,%4};" ::"l"(p), "r"(v.x), "r"(v.y), "r"(v.z), "r"(v.w) : "memory"); }
__device__ __forceinline__ uint4 ldg128(const void* p) { uint4 v; asm volatile("ld.global.nc.v4.u32 {%0,%1,%2,%3}, [%4];" : "=r"(v.x), "=r"(v.y), "=r"(v.z), "=r"(v.w) : "l"(p)); return v; }

__device__ __forceinline__ uint32_t enc(float v, uint32_t T) {
    uint32_t r; asm("lop3.b32 %0, %1, 1, %2, 0xBA;" : "=r"(r) : "r"(__float_as_uint(v)), "r"(T)); return r;
}

__device__ __forceinline__ void poll_splits(uint4 (&v)[4], uint2 (&ml)[4], const uint32_t* op, const uint32_t* mp, uint32_t T) {
    asm volatile(
        "{\n.reg .pred p0, p1, p2, p3, pa;\n.reg .b32 t1, t2, t3, n;\n"
        "mov.u32 n, 0;\n"
        "ld.relaxed.gpu.global.v4.u32 {%0,%1,%2,%3}, [%24];\n"
        "ld.relaxed.gpu.global.v4.u32 {%4,%5,%6,%7}, [%24+512];\n"
        "ld.relaxed.gpu.global.v4.u32 {%8,%9,%10,%11}, [%24+1024];\n"
        "ld.relaxed.gpu.global.v4.u32 {%12,%13,%14,%15}, [%24+1536];\n"
        "ld.relaxed.gpu.global.v2.u32 {%16,%17}, [%25];\n"
        "ld.relaxed.gpu.global.v2.u32 {%18,%19}, [%25+32];\n"
        "ld.relaxed.gpu.global.v2.u32 {%20,%21}, [%25+64];\n"
        "ld.relaxed.gpu.global.v2.u32 {%22,%23}, [%25+96];\n"
        "L_%=:\n"
        "lop3.b32 t1, %0, %1, %26, 0x7E;\nlop3.b32 t2, %2, %3, %26, 0x7E;\nlop3.b32 t3, %16, %17, %26, 0x7E;\nlop3.b32 t1, t1, t2, t3, 0xFE;\nand.b32 t1, t1, 1;\nsetp.ne.u32 p0, t1, 0;\n"
        "lop3.b32 t1, %4, %5, %26, 0x7E;\nlop3.b32 t2, %6, %7, %26, 0x7E;\nlop3.b32 t3, %18, %19, %26, 0x7E;\nlop3.b32 t1, t1, t2, t3, 0xFE;\nand.b32 t1, t1, 1;\nsetp.ne.u32 p1, t1, 0;\n"
        "lop3.b32 t1, %8, %9, %26, 0x7E;\nlop3.b32 t2, %10, %11, %26, 0x7E;\nlop3.b32 t3, %20, %21, %26, 0x7E;\nlop3.b32 t1, t1, t2, t3, 0xFE;\nand.b32 t1, t1, 1;\nsetp.ne.u32 p2, t1, 0;\n"
        "lop3.b32 t1, %12, %13, %26, 0x7E;\nlop3.b32 t2, %14, %15, %26, 0x7E;\nlop3.b32 t3, %22, %23, %26, 0x7E;\nlop3.b32 t1, t1, t2, t3, 0xFE;\nand.b32 t1, t1, 1;\nsetp.ne.u32 p3, t1, 0;\n"
        "or.pred pa, p0, p1;\nor.pred pa, pa, p2;\nor.pred pa, pa, p3;\n"
        "vote.sync.any.pred pa, pa, 0xffffffff;\n@!pa bra D_%=;\n"
        "@p0 ld.relaxed.gpu.global.v4.u32 {%0,%1,%2,%3}, [%24];\n"
        "@p1 ld.relaxed.gpu.global.v4.u32 {%4,%5,%6,%7}, [%24+512];\n"
        "@p2 ld.relaxed.gpu.global.v4.u32 {%8,%9,%10,%11}, [%24+1024];\n"
        "@p3 ld.relaxed.gpu.global.v4.u32 {%12,%13,%14,%15}, [%24+1536];\n"
        "@p0 ld.relaxed.gpu.global.v2.u32 {%16,%17}, [%25];\n"
        "@p1 ld.relaxed.gpu.global.v2.u32 {%18,%19}, [%25+32];\n"
        "@p2 ld.relaxed.gpu.global.v2.u32 {%20,%21}, [%25+64];\n"
        "@p3 ld.relaxed.gpu.global.v2.u32 {%22,%23}, [%25+96];\n"
        "add.u32 n, n, 1;\nsetp.lt.u32 pa, n, 4000000;\n@pa bra L_%=;\ntrap;\nD_%=:\n}"
        : "=r"(v[0].x), "=r"(v[0].y), "=r"(v[0].z), "=r"(v[0].w), "=r"(v[1].x), "=r"(v[1].y), "=r"(v[1].z), "=r"(v[1].w),
          "=r"(v[2].x), "=r"(v[2].y), "=r"(v[2].z), "=r"(v[2].w), "=r"(v[3].x), "=r"(v[3].y), "=r"(v[3].z), "=r"(v[3].w),
          "=r"(ml[0].x), "=r"(ml[0].y), "=r"(ml[1].x), "=r"(ml[1].y), "=r"(ml[2].x), "=r"(ml[2].y), "=r"(ml[3].x), "=r"(ml[3].y)
        : "l"(op), "l"(mp), "r"(T) : "memory");
}
__device__ __forceinline__ void poll_final(uint4 (&d)[6], const uint32_t* pa, const uint32_t* pb, uint32_t T) {
    asm volatile(
        "{\n.reg .pred p0, p1, p2, p3, p4, p5, pa;\n.reg .b32 t1, t2, n;\n"
        "mov.u32 n, 0;\n"
        "ld.relaxed.gpu.global.v4.u32 {%0,%1,%2,%3}, [%24];\n"
        "ld.relaxed.gpu.global.v4.u32 {%4,%5,%6,%7}, [%24+1024];\n"
        "ld.relaxed.gpu.global.v4.u32 {%8,%9,%10,%11}, [%24+2048];\n"
        "ld.relaxed.gpu.global.v4.u32 {%12,%13,%14,%15}, [%24+3072];\n"
        "ld.relaxed.gpu.global.v4.u32 {%16,%17,%18,%19}, [%25];\n"
        "ld.relaxed.gpu.global.v4.u32 {%20,%21,%22,%23}, [%25+1024];\n"
        "L_%=:\n"
        "lop3.b32 t1, %0, %1, %26, 0x7E;\nlop3.b32 t2, %2, %3, %26, 0x7E;\nor.b32 t1, t1, t2;\nand.b32 t1, t1, 1;\nsetp.ne.u32 p0, t1, 0;\n"
        "lop3.b32 t1, %4, %5, %26, 0x7E;\nlop3.b32 t2, %6, %7, %26, 0x7E;\nor.b32 t1, t1, t2;\nand.b32 t1, t1, 1;\nsetp.ne.u32 p1, t1, 0;\n"
        "lop3.b32 t1, %8, %9, %26, 0x7E;\nlop3.b32 t2, %10, %11, %26, 0x7E;\nor.b32 t1, t1, t2;\nand.b32 t1, t1, 1;\nsetp.ne.u32 p2, t1, 0;\n"
        "lop3.b32 t1, %12, %13, %26, 0x7E;\nlop3.b32 t2, %14, %15, %26, 0x7E;\nor.b32 t1, t1, t2;\nand.b32 t1, t1, 1;\nsetp.ne.u32 p3, t1, 0;\n"
        "lop3.b32 t1, %16, %17, %26, 0x7E;\nlop3.b32 t2, %18, %19, %26, 0x7E;\nor.b32 t1, t1, t2;\nand.b32 t1, t1, 1;\nsetp.ne.u32 p4, t1, 0;\n"
        "lop3.b32 t1, %20, %21, %26, 0x7E;\nlop3.b32 t2, %22, %23, %26, 0x7E;\nor.b32 t1, t1, t2;\nand.b32 t1, t1, 1;\nsetp.ne.u32 p5, t1, 0;\n"
        "or.pred pa, p0, p1;\nor.pred pa, pa, p2;\nor.pred pa, pa, p3;\nor.pred pa, pa, p4;\nor.pred pa, pa, p5;\n"
        "vote.sync.any.pred pa, pa, 0xffffffff;\n@!pa bra D_%=;\n"
        "@p0 ld.relaxed.gpu.global.v4.u32 {%0,%1,%2,%3}, [%24];\n"
        "@p1 ld.relaxed.gpu.global.v4.u32 {%4,%5,%6,%7}, [%24+1024];\n"
        "@p2 ld.relaxed.gpu.global.v4.u32 {%8,%9,%10,%11}, [%24+2048];\n"
        "@p3 ld.relaxed.gpu.global.v4.u32 {%12,%13,%14,%15}, [%24+3072];\n"
        "@p4 ld.relaxed.gpu.global.v4.u32 {%16,%17,%18,%19}, [%25];\n"
        "@p5 ld.relaxed.gpu.global.v4.u32 {%20,%21,%22,%23}, [%25+1024];\n"
        "add.u32 n, n, 1;\nsetp.lt.u32 pa, n, 4000000;\n@pa bra L_%=;\ntrap;\nD_%=:\n}"
        : "=r"(d[0].x), "=r"(d[0].y), "=r"(d[0].z), "=r"(d[0].w), "=r"(d[1].x), "=r"(d[1].y), "=r"(d[1].z), "=r"(d[1].w),
          "=r"(d[2].x), "=r"(d[2].y), "=r"(d[2].z), "=r"(d[2].w), "=r"(d[3].x), "=r"(d[3].y), "=r"(d[3].z), "=r"(d[3].w),
          "=r"(d[4].x), "=r"(d[4].y), "=r"(d[4].z), "=r"(d[4].w), "=r"(d[5].x), "=r"(d[5].y), "=r"(d[5].z), "=r"(d[5].w)
        : "l"(pa), "l"(pb), "r"(T) : "memory");
}
__device__ __forceinline__ uint4 poll_one(const uint32_t* ptr, uint32_t T) {
    uint4 v;
    asm volatile(
        "{\n.reg .pred p;\n.reg .b32 t1, t2, n;\nmov.u32 n, 0;\n"
        "L_%=:\n"
        "ld.relaxed.gpu.global.v4.u32 {%0,%1,%2,%3}, [%4];\n"
        "lop3.b32 t1, %0, %1, %5, 0x7E;\nlop3.b32 t2, %2, %3, %5, 0x7E;\nor.b32 t1, t1, t2;\nand.b32 t1, t1, 1;\nsetp.eq.u32 p, t1, 0;\n"
        "@p bra D_%=;\n"
        "add.u32 n, n, 1;\nsetp.lt.u32 p, n, 4000000;\n@p bra L_%=;\ntrap;\nD_%=:\n}"
        : "=r"(v.x), "=r"(v.y), "=r"(v.z), "=r"(v.w) : "l"(ptr), "r"(T) : "memory");
    return v;
}

__device__ __forceinline__ uint32_t pack_bf16(float lo, float hi) {
    uint32_t r; asm("cvt.rn.bf16x2.f32 %0, %1, %2;" : "=r"(r) : "f"(hi), "f"(lo)); return r;
}
__device__ __forceinline__ float bf_lo(uint32_t u) { return __uint_as_float(u << 16); }
__device__ __forceinline__ float bf_hi(uint32_t u) { return __uint_as_float(u & 0xffff0000u); }
__device__ __forceinline__ float rbf(float v) { return bf_lo(pack_bf16(v, 0.f)); }
__device__ __forceinline__ float ex2(float v) { float r; asm("ex2.approx.ftz.f32 %0, %1;" : "=f"(r) : "f"(v)); return r; }
__device__ __forceinline__ float rcp(float v) { float r; asm("rcp.approx.ftz.f32 %0, %1;" : "=f"(r) : "f"(v)); return r; }
__device__ __forceinline__ float sigmoidf_(float v) { return rcp(1.0f + ex2(-1.4426950408889634f * v)); }
constexpr float L2E = 1.4426950408889634f;

template <int KSTEPS>
__device__ __forceinline__ void gemv_slab(float (&acc)[4], uint32_t tile, int mt, uint32_t vec, int lane) {
    const int i = lane >> 3;
    const uint32_t a0 = tile + ((lane & 7) + 8 * (i >> 1)) * 128 + (((2 * mt + (i & 1)) ^ (lane & 7)) << 4);
#pragma unroll
    for (int ks = 0; ks < KSTEPS; ks++) {
        uint32_t a[4];
        ldsm4t(a, a0 + ks * 2048);
        uint32_t b0 = lds32(vec + ks * 32), b1 = lds32(vec + ks * 32 + 16);
        mma16816(acc, a[0], a[1], a[2], a[3], b0, b1);
    }
}

}
extern __shared__ __align__(1024) uint8_t smem_raw[];
namespace {

__global__ void __launch_bounds__(NTHREADS, 1) fused_decode_kernel(const __grid_constant__ Params p) {
    uint32_t sb;
    asm("mov.u32 %0, smem_raw;" : "=r"(sb));
    const int tid = threadIdx.x, lane = tid & 31;
    const int cta = blockIdx.x;
    const uint32_t bars = sb + OFF_BAR;
    auto BAR = [&](int i) { return bars + 8 * i; };
    const bool is_att = cta < NATT;
    bool one = false;
    if (tid < 32) {
        one = elect_one();
        if (one && is_att) {
#pragma unroll
            for (int n = 0; n < 4; n++) {
                mbar_init(BAR(BAR_WQ + n), 1);
                mbar_expect_tx(BAR(BAR_WQ + n), TILE / 2);
                tma2d_nohint(sb + OFF_W + n * (TILE / 2), &p.wq, cta * 32, n * 128, BAR(BAR_WQ + n));
            }
        }
    }
    const int warp = __shfl_sync(0xffffffffu, tid >> 5, 0);

    if (warp == W_PROD) {
        auto init_rest = [&](int nfull) {
#pragma unroll
            for (int s = 0; s < S; s++) { if (s >= nfull) mbar_init(BAR(BAR_FULL + s), 1); mbar_init(BAR(BAR_EMPTY + s), is_att ? 4 : 1); }
            mbar_init(BAR(BAR_WFREE), 4);
            mbar_init(BAR(BAR_LATE), 1); mbar_init(BAR(BAR_LATE + 1), 1); mbar_init(BAR(BAR_LATE + 2), 1);
            mbar_init(BAR(BAR_ISS), 1); mbar_init(BAR(BAR_KEEP), 1); mbar_init(BAR(BAR_ATT), 4); mbar_init(BAR(BAR_TAIL), 8);
            sts32(sb + OFF_EP + 4, 0);
            sts64(sb + OFF_EP + 16, 0u, clock32() + TA + WIN * TAU / 128);
            asm volatile("fence.mbarrier_init.release.cluster;" ::: "memory");
        };
        uint64_t pol;
        asm volatile("createpolicy.fractional.L2::evict_first.b64 %0, 1.0;" : "=l"(pol));
        if (is_att) {
            const int pair = cta >> 2, split = cta & 3;
            const int row0 = pair * SK + (((split & 1) << 1) | ((split >> 1) << 6)) * TK;
            auto tile_row = [&](int j) {
                return row0 + ((j & 1) | ((j & 2) << 4) | ((j & 4) << 2) | ((j & 24) >> 1)) * TK;
            };
            if (one) {
#pragma unroll
                for (int n = 0; n < NINIT; n++) {
                    mbar_init(BAR(BAR_FULL + n), 1);
                    mbar_expect_tx(BAR(BAR_FULL + n), TILE);
                    tma3d(sb + OFF_RING + n * TILE, (n & 1) ? &p.v : &p.k, tile_row(n >> 1), BAR(BAR_FULL + n), pol);
                }
                init_rest(NINIT);
            }
            __syncwarp();
            bar_arrive(1, NTHREADS);
            if (one) {
                int slot = NINIT, ph = 0;
                int wslot = 0, wph = 0, w = 0;
#pragma unroll 1
                for (int n = NINIT; n < 2 * NPAIR + 3; n++) {
                    const int need = n * 128 - WIN + (n < 2 * NPAIR ? max(n - (2 * NPAIR - 3), 0) * 32 : n == 2 * NPAIR ? HOLD0 : n == 2 * NPAIR + 1 ? HOLD1 : HOLD2);
                    uint32_t guard = 0;
                    while (true) {
                        while (w < n && w < 2 * NPAIR && mbar_test(BAR(BAR_FULL + wslot), wph)) {
                            if (++wslot == S) { wslot = 0; wph ^= 1; }
                            w++;
                            stv32(sb + OFF_EP + 4, w);
                        }
                        const int fl = n - w;
                        if (fl < CAPMIN && n >= CAPMIN + 2) break;
                        const uint2 an = ldv64(sb + OFF_EP + 16);
                        const int est = (int)an.x + ((min((int)(clock32() - an.y), 1 << 20) * (int)(128 * 4096 / TAU)) >> 12);
                        if (fl < CAPMAX && need <= est) break;
                        if (++guard > (1u << 28)) __trap();
                    }
                    if (n == 2 * NPAIR - 2) mbar_arrive(BAR(BAR_KEEP));
                    if (n == 2 * NPAIR - 8) mbar_wait(BAR(BAR_WFREE), 0);
                    if (n < 2 * NPAIR) {
                        if (n >= S) mbar_wait(BAR(BAR_EMPTY + slot), ph ^ 1);
                        mbar_expect_tx(BAR(BAR_FULL + slot), TILE);
                        tma3d(sb + OFF_RING + slot * TILE, (n & 1) ? &p.v : &p.k, tile_row(n >> 1), BAR(BAR_FULL + slot), pol);
                        if (++slot == S) { slot = 0; ph ^= 1; }
                    } else {
                        const int j = n - 2 * NPAIR;
                        mbar_expect_tx(BAR(BAR_LATE + j), j < 2 ? TILE : 112 * 128);
                        if (j < 2) tma2d(sb + OFF_W + j * TILE, &p.wo, (cta & 3) * 128 + j * 64, (cta >> 2) * 128, BAR(BAR_LATE + j), pol);
                        else       tma2d(sb + OFF_W + 2 * TILE, &p.wd, (cta & 7) * 64, (cta >> 3) * 112, BAR(BAR_LATE + 2), pol);
                    }
                }
                sts32(sb + OFF_EP + 8, clock32());
                mbar_arrive(BAR(BAR_ISS));
                stv32(sb + OFF_EP + 4, 2 * NPAIR);
            }
        } else {
            const int col0 = (cta - NATT) * 448;
            if (one) {
#pragma unroll
                for (int n = 0; n < GCAP; n++) {
                    mbar_init(BAR(BAR_FULL + n), 1);
                    mbar_expect_tx(BAR(BAR_FULL + n), TILE);
                    tma2d(sb + OFF_RING + n * TILE, &p.wg, col0 + n * 64, 0, BAR(BAR_FULL + n), pol);
                }
                init_rest(GCAP);
            }
            __syncwarp();
            bar_arrive(1, NTHREADS);
            if (one) {
#pragma unroll 1
                for (int n = GCAP; n < GLU_TILES; n++) {
                    const int w = n - GCAP;
                    mbar_wait(BAR(BAR_FULL + w % GLU_S), (w / GLU_S) & 1);
                    const int slot = n % GLU_S, r = n / GLU_S;
                    if (r > 0) mbar_wait(BAR(BAR_EMPTY + slot), (r & 1) ^ 1);
                    mbar_expect_tx(BAR(BAR_FULL + slot), TILE);
                    tma2d(sb + OFF_RING + slot * TILE, (r & 1) ? &p.wu : &p.wg, col0 + slot * 64, (r >> 1) * 128, BAR(BAR_FULL + slot), pol);
                }
            }
        }
        return;
    }

    const uint32_t ck0 = clock32();
    if (warp >= W_PRJ) {
        const int j = tid - W_PRJ * 32;
        uint4 v0 = ldg128(p.x + j * 8), v1 = ldg128(p.x + 1024 + j * 8);
        uint32_t ep = 0;
        if (j == 0) ep = ldr32(p.scr->epoch);
        sts128(sb + OFF_XS + (j >> 6) * XS_PITCH + (j & 63) * 16, v0);
        sts128(sb + OFF_XS + (2 + (j >> 6)) * XS_PITCH + (j & 63) * 16, v1);
        if (j == 0) sts32(sb + OFF_EP, ep);
    }
    uint4 gw0, gw1;
    if (warp < W_ATT) { gw0 = ldg128(p.gate_w + lane * 16); gw1 = ldg128(p.gate_w + lane * 16 + 8); }
    bar_sync(1, NTHREADS);
    const uint32_t epoch = lds32(sb + OFF_EP);
    const uint32_t T = (epoch + 1) & 1;
    Scratch* const buf = p.scr;
    const int g = lane >> 2, t = lane & 3;

    if (!is_att) {
        if (warp >= W_ATT && warp < W_ATT + GLU_S) {
            const int gw = warp - W_ATT;
            float acc[2][4][4];
#pragma unroll
            for (int m = 0; m < 2; m++)
#pragma unroll
                for (int mt = 0; mt < 4; mt++) { acc[m][mt][0] = acc[m][mt][1] = acc[m][mt][2] = acc[m][mt][3] = 0.f; }
            const uint32_t tile = sb + OFF_RING + gw * TILE;
            const uint32_t vec = sb + OFF_XS + (g & 3) * XS_PITCH + t * 4;
#pragma unroll 1
            for (int rb = 0; rb < 4; rb++) {
#pragma unroll
                for (int m = 0; m < 2; m++) {
                    mbar_wait(BAR(BAR_FULL + gw), m);
#pragma unroll
                    for (int mt = 0; mt < 4; mt++) gemv_slab<8>(acc[m][mt], tile, mt, vec + rb * 256, lane);
                    __syncwarp();
                    if (lane == 0) mbar_arrive(BAR(BAR_EMPTY + gw));
                }
            }
            if (t < 2) {
                uint32_t* hp = buf->h + (2 * t) * FF + (cta - NATT) * 448 + gw * 64 + g;
#pragma unroll
                for (int mt = 0; mt < 4; mt++)
#pragma unroll
                    for (int c = 0; c < 4; c++) {
                        const float gg = rbf(acc[0][mt][c]), uu = rbf(acc[1][mt][c]);
                        const float hh = rbf(rbf(sigmoidf_(gg)) * uu);
                        str32(hp + (c & 1) * FF + mt * 16 + (c >> 1) * 8, enc(hh, T));
                    }
            }
        }
        return;
    }

    if (warp >= W_ATT && warp < W_CMB) {
        const int aw = warp - W_ATT, at = tid - W_ATT * 32;
        const int pair = cta >> 2, split = cta & 3, b = pair >> 3, hkv = pair & 7;
        const int oidx = ((hkv * 4 + aw) * NB + b) * OBLK;
        uint32_t* optr = buf->o + ((hkv * 4 + 2 * t) * NB + b) * OBLK + split * DH + 32 * aw + 4 * g;
        uint32_t* mlptr = buf->o + oidx + 4 * DH + split * 8 + 4 * lane;
        const uint32_t* hptr = buf->h + (at / 28) * FF + (cta >> 3) * 112 + (at % 28) * 4;
        uint32_t hdst = sb + OFF_HS + (at / 28) * HS_PITCH + (at % 28) * 8;
        uint32_t* bptr = buf->b + (((2 * t) * 32 + (cta & 7) * 4 + aw) * 16 + (cta >> 3)) * 32 + 2 * g;
        uint32_t rdst = sb + OFF_RED + (aw * 128 + g * 2 + t) * 16;
        uint32_t rsrc = sb + OFF_RED + (aw * 32 + g * 2 + (t & 1)) * 16;
        pin(optr); pin(mlptr); pin(hptr); pin(hdst); pin(bptr); pin(rdst); pin(rsrc);
        {
            const uint32_t N = T ^ 1;
            if (lane < 2) str128(mlptr, make_uint4(N, N, N, N));
            if (t < 2) {
                str128(optr, make_uint4(N, N, N, N)); str128(optr + NB * OBLK, make_uint4(N, N, N, N));
                str64(bptr, N, N); str64(bptr + 16384, N, N);
            }
        }
        {
            const uint32_t* qsrc = buf->q + (b * HKV + hkv) * QBLK + 4 * at;
            mbar_wait(BAR(BAR_WFREE), 0);
            while (clock32() - ck0 < (uint32_t)QD) { }
            const uint4 v = poll_one(qsrc, T);
            sts64(sb + OFF_QS + (aw * QS_PITCH + 2 * lane) * 4, __byte_perm(v.x, v.y, 0x7632), __byte_perm(v.z, v.w, 0x7632));
        }
        bar_sync(2, 128);
        uint32_t qa[16], qz[16];
#pragma unroll
        for (int c = 0; c < 16; c++) {
            uint32_t v = lds32(sb + OFF_QS + ((g & 3) * QS_PITCH + 4 * c + t) * 4);
            qa[c] = g < 4 ? v : 0u;
            qz[c] = 0u;
            pin(qz[c]);
        }
        float o[8][4];
#pragma unroll
        for (int mt = 0; mt < 8; mt++) { o[mt][0] = o[mt][1] = o[mt][2] = o[mt][3] = 0.f; }
        float m = -INFINITY, l = 0.f;
        const int i = lane >> 3;
        uint32_t koff = (aw * 16 + (lane & 7)) * 128 + ((i ^ (lane & 7)) << 4);
        uint32_t voff = (aw * 16 + (lane & 7) + 8 * (i >> 1)) * 128 + (((i & 1) ^ (lane & 7)) << 4);
        pin(koff); pin(voff);
        int slot = 0, ph = 0;
        uint32_t pb0, pb1;
#pragma unroll 1
        for (int j = 0;; j++) {
            mbar_wait(BAR(BAR_FULL + slot), ph);
            const uint32_t kb = sb + OFF_RING + slot * TILE;
            float s0[4] = {0.f, 0.f, 0.f, 0.f}, s1[4] = {0.f, 0.f, 0.f, 0.f};
#pragma unroll
            for (int cq = 0; cq < 4; cq++) {
                uint32_t r0[4], r1[4];
                const uint32_t a = kb + (cq >> 1) * 8192 + (koff ^ ((cq & 1) << 6));
                ldsm4(r0, a);
                ldsm4(r1, a + 1024);
                mma16816(s0, qa[4 * cq], qz[4 * cq], qa[4 * cq + 1], qz[4 * cq + 1], r0[0], r0[1]);
                mma16816(s1, qa[4 * cq], qz[4 * cq], qa[4 * cq + 1], qz[4 * cq + 1], r1[0], r1[1]);
                mma16816(s0, qa[4 * cq + 2], qz[4 * cq + 2], qa[4 * cq + 3], qz[4 * cq + 3], r0[2], r0[3]);
                mma16816(s1, qa[4 * cq + 2], qz[4 * cq + 2], qa[4 * cq + 3], qz[4 * cq + 3], r1[2], r1[3]);
            }
            __syncwarp();
            if (lane == 0) mbar_arrive(BAR(BAR_EMPTY + slot));
            if (++slot == S) { slot = 0; ph ^= 1; }
            constexpr float SCALE = 0.08838834764831845f;
            uint32_t u0 = pack_bf16(s0[0], s0[1]), u1 = pack_bf16(s1[0], s1[1]);
            u0 = pack_bf16(bf_lo(u0) * SCALE, bf_hi(u0) * SCALE);
            u1 = pack_bf16(bf_lo(u1) * SCALE, bf_hi(u1) * SCALE);
            const float v0 = bf_lo(u0), v1 = bf_hi(u0), v2 = bf_lo(u1), v3 = bf_hi(u1);
            float mx = fmaxf(fmaxf(v0, v1), fmaxf(v2, v3));
            mx = fmaxf(mx, __shfl_xor_sync(0xffffffffu, mx, 1));
            mx = fmaxf(mx, __shfl_xor_sync(0xffffffffu, mx, 2));
            if (j == NPAIR - 1) {
                if (t == 0 && g < 4) stsf(sb + OFF_ML + (g * 4 + aw) * 4, fmaxf(m, mx));
                bar_sync(2, 128);
                const float4 w = ldsf4(sb + OFF_ML + (g & 3) * 16);
                mx = fmaxf(fmaxf(w.x, w.y), fmaxf(w.z, w.w));
            }
            if (__any_sync(0xffffffffu, mx > m)) {
                const float mn = fmaxf(m, mx);
                const float al = ex2((m - mn) * L2E);
                m = mn;
                l *= al;
                const float f0 = __shfl_sync(0xffffffffu, al, 8 * t), f1 = __shfl_sync(0xffffffffu, al, 8 * t + 4);
#pragma unroll
                for (int mt = 0; mt < 8; mt++) { o[mt][0] *= f0; o[mt][1] *= f1; o[mt][2] *= f0; o[mt][3] *= f1; }
            }
            const float mb = m * L2E;
            const float p0 = ex2(fmaf(v0, L2E, -mb)), p1 = ex2(fmaf(v1, L2E, -mb));
            const float p2 = ex2(fmaf(v2, L2E, -mb)), p3 = ex2(fmaf(v3, L2E, -mb));
            l += (p0 + p1) + (p2 + p3);
            pb0 = pack_bf16(p0, p1); pb1 = pack_bf16(p2, p3);
            if (j == NPAIR - 1) break;
            mbar_wait(BAR(BAR_FULL + slot), ph);
            const uint32_t vb = sb + OFF_RING + slot * TILE;
#pragma unroll
            for (int mt = 0; mt < 8; mt++) {
                uint32_t a[4];
                ldsm4t(a, vb + (mt >> 2) * 8192 + (voff ^ ((mt & 3) << 5)));
                mma16816(o[mt], a[0], a[1], a[2], a[3], pb0, pb1);
            }
            __syncwarp();
            if (lane == 0) mbar_arrive(BAR(BAR_EMPTY + slot));
            if (++slot == S) { slot = 0; ph ^= 1; }
        }
        l += __shfl_xor_sync(0xffffffffu, l, 1);
        l += __shfl_xor_sync(0xffffffffu, l, 2);
        if (t < 2) {
#pragma unroll
            for (int mt = 0; mt < 8; mt++)
                sts128(rdst + mt * 256, make_uint4(__float_as_uint(o[mt][0]), __float_as_uint(o[mt][1]), __float_as_uint(o[mt][2]), __float_as_uint(o[mt][3])));
        }
        sts64(sb + OFF_QS + aw * 256 + lane * 8, pb0, pb1);
        if (t == 0 && g < 4) stsf(sb + OFF_ML + 64 + (g * 4 + aw) * 4, l);
        bar_sync(2, 128);
        {
            float c[4][4];
            uint2 pk[4];
#pragma unroll
            for (int k = 0; k < 4; k++)
                asm volatile("ld.shared.v2.u32 {%0,%1}, [%2];" : "=r"(pk[k].x), "=r"(pk[k].y) : "r"(sb + OFF_QS + k * 256 + lane * 8) : "memory");
#pragma unroll
            for (int e = 0; e < 2; e++) {
                const float4 x0 = ldsf4(rsrc + e * 256), x1 = ldsf4(rsrc + e * 256 + 2048), x2 = ldsf4(rsrc + e * 256 + 4096), x3 = ldsf4(rsrc + e * 256 + 6144);
                c[e][0] = x0.x + x1.x; c[e][1] = x0.y + x1.y; c[e][2] = x0.z + x1.z; c[e][3] = x0.w + x1.w;
                c[2 + e][0] = x2.x + x3.x; c[2 + e][1] = x2.y + x3.y; c[2 + e][2] = x2.z + x3.z; c[2 + e][3] = x2.w + x3.w;
            }
            const float4 mw = ldsf4(sb + OFF_ML + aw * 16), lw = ldsf4(sb + OFF_ML + 64 + aw * 16);
            if (lane < 2) str128(mlptr, make_uint4(enc(fmaxf(fmaxf(mw.x, mw.y), fmaxf(mw.z, mw.w)), T), enc((lw.x + lw.y) + (lw.z + lw.w), T), T, T));
            uint32_t va = sb + OFF_RING + slot * TILE + (aw >> 1) * 8192 + ((lane & 7) + 8 * (i >> 1)) * 128 + (((4 * (aw & 1) + (i & 1)) ^ (lane & 7)) << 4);
            pin(va);
            mbar_wait(BAR(BAR_FULL + slot), ph);
#pragma unroll
            for (int k = 0; k < 4; k++) {
                uint32_t a0[4], a1[4];
                ldsm4t(a0, va + k * 2048);
                ldsm4t(a1, (va ^ 32) + k * 2048);
                mma16816(c[2 * (k & 1)], a0[0], a0[1], a0[2], a0[3], pk[k].x, pk[k].y);
                mma16816(c[2 * (k & 1) + 1], a1[0], a1[1], a1[2], a1[3], pk[k].x, pk[k].y);
            }
            if (t < 2) {
                str128(optr, make_uint4(enc(c[0][0] + c[2][0], T), enc(c[0][2] + c[2][2], T), enc(c[1][0] + c[3][0], T), enc(c[1][2] + c[3][2], T)));
                str128(optr + NB * OBLK, make_uint4(enc(c[0][1] + c[2][1], T), enc(c[0][3] + c[2][3], T), enc(c[1][1] + c[3][1], T), enc(c[1][3] + c[3][3], T)));
            }
            if (lane == 0) mbar_arrive(BAR(BAR_ATT));
        }
        if (at < 112) {
            const uint4 v = poll_one(hptr, T);
            sts64(hdst, __byte_perm(v.x, v.y, 0x7632), __byte_perm(v.z, v.w, 0x7632));
        }
        bar_sync(2, 128);
        float acc[4] = {0.f, 0.f, 0.f, 0.f};
        {
            uint32_t hb[4][4], a[7][4];
#pragma unroll
            for (int k = 0; k < 4; k++) ldsm4(hb[k], sb + OFF_HS + (lane & 3) * HS_PITCH + i * 16 + k * 64);
            uint32_t a0 = sb + OFF_W + 2 * TILE + ((lane & 7) + 8 * (i >> 1)) * 128 + (((2 * aw + (i & 1)) ^ (lane & 7)) << 4);
            pin(a0);
            mbar_wait(BAR(BAR_LATE + 2), 0);
#pragma unroll
            for (int k = 0; k < 7; k++) ldsm4t(a[k], a0 + k * 2048);
            float acc2[4] = {0.f, 0.f, 0.f, 0.f};
#pragma unroll
            for (int k = 0; k < 7; k++)
                mma16816((k & 1) ? acc2 : acc, a[k][0], a[k][1], a[k][2], a[k][3], hb[k >> 1][2 * (k & 1)], hb[k >> 1][2 * (k & 1) + 1]);
#pragma unroll
            for (int u = 0; u < 4; u++) acc[u] += acc2[u];
        }
        if (t < 2) {
            str64(bptr, enc(acc[0], T), enc(acc[2], T)); str64(bptr + 16384, enc(acc[1], T), enc(acc[3], T));
        }
        if (lane == 0) mbar_arrive(BAR(BAR_TAIL));
    } else if (warp >= W_CMB && warp < W_PRJ) {
        const int tw = warp - W_CMB, head = cta >> 2;
        {
            const uint32_t* op = buf->o + (head * 4 + tw) * OBLK + 4 * lane;
            const uint32_t* mp = buf->o + (head * 4 + tw) * OBLK + 4 * DH;
            pin(op); pin(mp);
            uint4 v[4];
            uint2 ml[4];
            mbar_wait(BAR(BAR_ATT), 0);
            mbar_wait(BAR(BAR_ISS), 0);
            for (const uint32_t t0 = lds32(sb + OFF_EP + 8); clock32() - t0 < (uint32_t)CD;) { }
            poll_splits(v, ml, op, mp, T);
            const float m0 = __uint_as_float(ml[0].x & ~1u), m1 = __uint_as_float(ml[1].x & ~1u);
            const float m2 = __uint_as_float(ml[2].x & ~1u), m3 = __uint_as_float(ml[3].x & ~1u);
            const float M = fmaxf(fmaxf(m0, m1), fmaxf(m2, m3));
            const float e0 = ex2((m0 - M) * L2E), e1 = ex2((m1 - M) * L2E), e2 = ex2((m2 - M) * L2E), e3 = ex2((m3 - M) * L2E);
            const float inv = rcp(fmaf(e0, __uint_as_float(ml[0].y), e1 * __uint_as_float(ml[1].y)) + fmaf(e2, __uint_as_float(ml[2].y), e3 * __uint_as_float(ml[3].y)));
            const float r0 = fmaf(__uint_as_float(v[0].x), e0, __uint_as_float(v[1].x) * e1) + fmaf(__uint_as_float(v[2].x), e2, __uint_as_float(v[3].x) * e3);
            const float r1 = fmaf(__uint_as_float(v[0].y), e0, __uint_as_float(v[1].y) * e1) + fmaf(__uint_as_float(v[2].y), e2, __uint_as_float(v[3].y) * e3);
            const float r2 = fmaf(__uint_as_float(v[0].z), e0, __uint_as_float(v[1].z) * e1) + fmaf(__uint_as_float(v[2].z), e2, __uint_as_float(v[3].z) * e3);
            const float r3 = fmaf(__uint_as_float(v[0].w), e0, __uint_as_float(v[1].w) * e1) + fmaf(__uint_as_float(v[2].w), e2, __uint_as_float(v[3].w) * e3);
            const uint32_t od = sb + OFF_OS + tw * OS_PITCH + (lane >> 3) * 64 + (lane & 7) * 4;
            sts32(od, pack_bf16(r0 * inv, r1 * inv));
            sts32(od + 32, pack_bf16(r2 * inv, r3 * inv));
        }
        bar_arrive(4, 256);
    } else if (warp >= W_PRJ) {
        const int tw = warp - W_PRJ;
        const int head = cta >> 2;
        uint32_t* aptr = buf->a + (((2 * t) * 32 + (cta & 3) * 8 + 2 * tw) * 32 + head) * 32 + 2 * g;
        uint32_t* qptr = buf->q + (tw * HKV + (cta >> 4)) * QBLK + (cta & 15) * 32 + lane;
        pin(aptr);
        str32(qptr, T ^ 1);
        if (t < 2) {
#pragma unroll
            for (int u = 0; u < 4; u++) str64(aptr + (u & 1) * 1024 + (u >> 1) * 32768, T ^ 1, T ^ 1);
        }
        {
            mbar_wait(BAR(BAR_WQ + tw), 0);
            const int i = lane >> 3;
            const int r0 = (lane & 7) + 8 * (i >> 1);
            const uint32_t a0 = sb + OFF_W + tw * (TILE / 2) + r0 * 64;
            const uint32_t x0 = ((i & 1) ^ ((r0 >> 1) & 3)) << 4;
            const uint32_t vec = sb + OFF_XS + (g & 3) * XS_PITCH + tw * 256 + t * 4;
            float c0[4] = {0.f, 0.f, 0.f, 0.f}, c1[4] = {0.f, 0.f, 0.f, 0.f};
#pragma unroll
            for (int k = 0; k < 8; k++) {
                uint32_t a[4], a2[4];
                ldsm4t(a, a0 + k * 1024 + x0);
                ldsm4t(a2, a0 + k * 1024 + (x0 ^ 32));
                const uint32_t b0 = lds32(vec + k * 32), b1 = lds32(vec + k * 32 + 16);
                mma16816(c0, a[0], a[1], a[2], a[3], b0, b1);
                mma16816(c1, a2[0], a2[1], a2[2], a2[3], b0, b1);
            }
            if (t < 2) {
                const uint32_t rb = sb + OFF_QR + tw * 512 + (g * 4 + 2 * t) * 4;
                stsf2(rb, c0[0], c0[1]); stsf2(rb + 128, c0[2], c0[3]);
                stsf2(rb + 256, c1[0], c1[1]); stsf2(rb + 384, c1[2], c1[3]);
            }
            bar_sync(3, 128);
            {
                const uint32_t src = sb + OFF_QR + (lane * 4 + tw) * 4;
                const float qv = (ldsf(src) + ldsf(src + 512)) + (ldsf(src + 1024) + ldsf(src + 1536));
                str32(qptr, enc(rbf(qv), T));
            }
            __syncwarp();
            if (lane == 0) mbar_arrive(BAR(BAR_WFREE));
        }
        float c[4][4] = {};
        {
            const int i = lane >> 3;
            const int r7 = 4 * (i >> 1) + ((lane & 7) >> 1);
            const uint32_t a0 = sb + OFF_W + (tw >> 1) * TILE + (r7 + 8 * (lane & 1)) * 128 + (((4 * (tw & 1) + (i & 1)) ^ r7) << 4);
            uint32_t a[2][8][4];
            mbar_wait(BAR(BAR_LATE + (tw >> 1)), 0);
#pragma unroll
            for (int k = 0; k < 8; k++) { ldsm4t(a[0][k], a0 + k * 2048); ldsm4t(a[1][k], (a0 ^ 32) + k * 2048); }
            bar_sync(4, 256);
            const uint32_t vb = sb + OFF_OS + (lane & 3) * OS_PITCH + i * 16;
#pragma unroll
            for (int k = 0; k < 4; k++) {
                uint32_t bf[4];
                ldsm4(bf, vb + k * 64);
                mma16816(c[0], a[0][2 * k][0], a[0][2 * k][1], a[0][2 * k][2], a[0][2 * k][3], bf[0], bf[1]);
                mma16816(c[1], a[1][2 * k][0], a[1][2 * k][1], a[1][2 * k][2], a[1][2 * k][3], bf[0], bf[1]);
                mma16816(c[2], a[0][2 * k + 1][0], a[0][2 * k + 1][1], a[0][2 * k + 1][2], a[0][2 * k + 1][3], bf[2], bf[3]);
                mma16816(c[3], a[1][2 * k + 1][0], a[1][2 * k + 1][1], a[1][2 * k + 1][2], a[1][2 * k + 1][3], bf[2], bf[3]);
            }
        }
        if (t < 2) {
#pragma unroll
            for (int mt = 0; mt < 2; mt++) {
                str64(aptr + mt * 1024, enc(c[mt][0] + c[2 + mt][0], T), enc(c[mt][2] + c[2 + mt][2], T));
                str64(aptr + mt * 1024 + 32768, enc(c[mt][1] + c[2 + mt][1], T), enc(c[mt][3] + c[2 + mt][3], T));
            }
        }
        if (lane == 0) mbar_arrive(BAR(BAR_TAIL));
    } else if (warp == W_FIN + 1) {
        asm volatile("" ::"l"(smem_raw));
        float z[4] = {0.f, 0.f, 0.f, 0.f};
        mbar_wait(BAR(BAR_KEEP), 0);
        for (uint32_t n = 0; !__any_sync(0xffffffffu, mbar_test(BAR(BAR_TAIL), 0)); n++) {
            asm volatile("mma.sync.aligned.m16n8k16.row.col.f32.bf16.bf16.f32 {%0,%1,%2,%3}, {%4,%4,%4,%4}, {%4,%4}, {%0,%1,%2,%3};"
                         : "+f"(z[0]), "+f"(z[1]), "+f"(z[2]), "+f"(z[3]) : "r"(lane));
            __nanosleep(200);
            if (n > SPIN_LIMIT) __trap();
        }
        if (z[0] + z[1] + z[2] + z[3] == 1.0f) stsf(sb + OFF_EP + 12, z[0]);
    } else if (warp == W_PACE) {
        if (lane == 0) {
            uint32_t last = 0, n = 0, ft = clock32();
            int fa = -100000;
            if (cta == 0) str32(buf->prog + 32 * (T ^ 1), 0);
            while (last < 2 * NPAIR) {
                const uint32_t w = ldv32(sb + OFF_EP + 4);
                if (w == 0) { __nanosleep(100); if (++n > SPIN_LIMIT) __trap(); continue; }
                uint32_t old;
                asm volatile("atom.relaxed.gpu.global.add.u32 %0, [%1], %2;" : "=r"(old) : "l"(buf->prog + 32 * T), "r"(w - last) : "memory");
                const uint32_t a = old + (w - last);
                last = w;
                if (a >= NATT) {
                    const uint32_t now = clock32() - RET;
                    const int pred = fa + ((min((int)(now - ft), 1 << 20) * (int)(128 * 4096 / TAU)) >> 12);
                    const int e = (int)a - pred;
                    fa = (e > 128 || e < -128) ? (int)a : pred + (e >> 2);
                    ft = now;
                    stv64(sb + OFF_EP + 16, (uint32_t)fa, now);
                }
                __nanosleep(100);
                if (++n > SPIN_LIMIT) __trap();
            }
        }
    } else if (warp == W_FIN) {
        const int ob = cta >> 5;
        float gate;
        {
            const uint4 x0 = lds128(sb + OFF_XS + ob * XS_PITCH + lane * 32), x1 = lds128(sb + OFF_XS + ob * XS_PITCH + lane * 32 + 16);
            const uint32_t xs[8] = {x0.x, x0.y, x0.z, x0.w, x1.x, x1.y, x1.z, x1.w};
            const uint32_t ws[8] = {gw0.x, gw0.y, gw0.z, gw0.w, gw1.x, gw1.y, gw1.z, gw1.w};
            float s = 0.f;
#pragma unroll
            for (int u = 0; u < 8; u++) {
                uint32_t pr;
                asm("mul.rn.bf16x2 %0, %1, %2;" : "=r"(pr) : "r"(xs[u]), "r"(ws[u]));
                s += bf_lo(pr) + bf_hi(pr);
            }
#pragma unroll
            for (int d = 16; d; d >>= 1) s += __shfl_xor_sync(0xffffffffu, s, d);
            gate = rbf(sigmoidf_(rbf(s)));
        }
        const uint32_t* pa = buf->a + cta * 1024 + (lane >> 2) * 32 + (lane & 3) * 4;
        const uint32_t* pb = buf->b + cta * 512 + (lane >> 2) * 32 + (lane & 3) * 4;
        __nv_bfloat16* outp = p.out + cta * 16 + lane * 2;
        const float gsel = lane < 16 ? gate : 1.0f - gate;
        uint32_t g2 = pack_bf16(gsel, gsel);
        uint32_t first = cta == 0 && lane == 0;
        pin(pa); pin(pb); pin(outp); pin(g2); pin(first);
        uint4 d[6];
        mbar_wait(BAR(BAR_TAIL), 0);
        for (const uint32_t t0 = lds32(sb + OFF_EP + 8); clock32() - t0 < (uint32_t)FD;) { }
        poll_final(d, pa, pb, T);
        if (first) str32(const_cast<uint32_t*>(pa) + (offsetof(Scratch, epoch) - offsetof(Scratch, a)) / 4, epoch + 1);
        const float ra[4] = {(__uint_as_float(d[0].x) + __uint_as_float(d[1].x)) + (__uint_as_float(d[2].x) + __uint_as_float(d[3].x)),
                             (__uint_as_float(d[0].y) + __uint_as_float(d[1].y)) + (__uint_as_float(d[2].y) + __uint_as_float(d[3].y)),
                             (__uint_as_float(d[0].z) + __uint_as_float(d[1].z)) + (__uint_as_float(d[2].z) + __uint_as_float(d[3].z)),
                             (__uint_as_float(d[0].w) + __uint_as_float(d[1].w)) + (__uint_as_float(d[2].w) + __uint_as_float(d[3].w))};
        const float rb[4] = {__uint_as_float(d[4].x) + __uint_as_float(d[5].x), __uint_as_float(d[4].y) + __uint_as_float(d[5].y),
                             __uint_as_float(d[4].z) + __uint_as_float(d[5].z), __uint_as_float(d[4].w) + __uint_as_float(d[5].w)};
        float r[4];
#pragma unroll
        for (int u = 0; u < 4; u++)
            r[u] = (lane < 16 ? ra[u] : rb[u]) + __shfl_xor_sync(0xffffffffu, lane < 16 ? rb[u] : ra[u], 16);
#pragma unroll
        for (int u = 0; u < 4; u++) {
            r[u] += __shfl_xor_sync(0xffffffffu, r[u], 4);
            r[u] += __shfl_xor_sync(0xffffffffu, r[u], 8);
        }
        uint32_t w0 = pack_bf16(r[0], r[2]), w1 = pack_bf16(r[1], r[3]);
        asm("mul.rn.bf16x2 %0, %0, %1;" : "+r"(w0) : "r"(g2));
        asm("mul.rn.bf16x2 %0, %0, %1;" : "+r"(w1) : "r"(g2));
        const uint32_t x0 = __shfl_xor_sync(0xffffffffu, w0, 16), x1 = __shfl_xor_sync(0xffffffffu, w1, 16);
        asm("add.rn.bf16x2 %0, %0, %1;" : "+r"(w0) : "r"(x0));
        asm("add.rn.bf16x2 %0, %0, %1;" : "+r"(w1) : "r"(x1));
        if (lane < 8) asm volatile("st.global.u32 [%0], %1;" ::"l"(outp), "r"(lane < 4 ? w0 : w1) : "memory");
    }
}

typedef CUresult (*EncodeFn)(CUtensorMap*, CUtensorMapDataType, cuuint32_t, void*, const cuuint64_t*, const cuuint64_t*,
                             const cuuint32_t*, const cuuint32_t*, CUtensorMapInterleave, CUtensorMapSwizzle,
                             CUtensorMapL2promotion, CUtensorMapFloatOOBfill);

void make2d(EncodeFn enc, CUtensorMap* m, const void* ptr, uint64_t cols, uint64_t rows, uint32_t bc, uint32_t br,
            CUtensorMapSwizzle sw, CUtensorMapL2promotion pr) {
    cuuint64_t gd[2] = {cols, rows}, gs[1] = {cols * 2};
    cuuint32_t bd[2] = {bc, br}, es[2] = {1, 1};
    enc(m, CU_TENSOR_MAP_DATA_TYPE_BFLOAT16, 2, const_cast<void*>(ptr), gd, gs, bd, es, CU_TENSOR_MAP_INTERLEAVE_NONE, sw, pr,
        CU_TENSOR_MAP_FLOAT_OOB_FILL_NONE);
}
void make_kv(EncodeFn enc, CUtensorMap* m, const void* ptr) {
    cuuint64_t gd[3] = {64, (cuuint64_t)NB * HKV * SK, 2}, gs[2] = {256, 128};
    cuuint32_t bd[3] = {64, TK, 2}, es[3] = {1, 1, 1};
    enc(m, CU_TENSOR_MAP_DATA_TYPE_BFLOAT16, 3, const_cast<void*>(ptr), gd, gs, bd, es, CU_TENSOR_MAP_INTERLEAVE_NONE,
        CU_TENSOR_MAP_SWIZZLE_128B, CU_TENSOR_MAP_L2_PROMOTION_L2_256B, CU_TENSOR_MAP_FLOAT_OOB_FILL_NONE);
}

}

extern "C" void kernel_launch(void* const* d_in, const int* in_sizes, int n_in, void* d_out, int out_size) {
    (void)in_sizes; (void)n_in; (void)out_size;
    static EncodeFn enc = nullptr;
    static Scratch* scr = nullptr;
    if (!enc) {
        void* fn = nullptr;
        cudaDriverEntryPointQueryResult qr;
        cudaGetDriverEntryPoint("cuTensorMapEncodeTiled", &fn, cudaEnableDefault, &qr);
        enc = (EncodeFn)fn;
        cudaGetSymbolAddress((void**)&scr, g_scratch);
        cudaFuncSetAttribute(fused_decode_kernel, cudaFuncAttributeMaxDynamicSharedMemorySize, SMEM_BYTES);
    }
    Params p;
    make_kv(enc, &p.k, d_in[1]);
    make_kv(enc, &p.v, d_in[2]);
    make2d(enc, &p.wq, d_in[3], HQ * DH, DM, 32, 128, CU_TENSOR_MAP_SWIZZLE_64B, CU_TENSOR_MAP_L2_PROMOTION_L2_128B);
    make2d(enc, &p.wo, d_in[4], DM, HQ * DH, 64, 128, CU_TENSOR_MAP_SWIZZLE_128B, CU_TENSOR_MAP_L2_PROMOTION_L2_128B);
    make2d(enc, &p.wg, d_in[6], FF, DM, 64, 128, CU_TENSOR_MAP_SWIZZLE_128B, CU_TENSOR_MAP_L2_PROMOTION_L2_128B);
    make2d(enc, &p.wu, d_in[7], FF, DM, 64, 128, CU_TENSOR_MAP_SWIZZLE_128B, CU_TENSOR_MAP_L2_PROMOTION_L2_128B);
    make2d(enc, &p.wd, d_in[8], DM, FF, 64, 112, CU_TENSOR_MAP_SWIZZLE_128B, CU_TENSOR_MAP_L2_PROMOTION_L2_128B);
    p.x = (const __nv_bfloat16*)d_in[0];
    p.gate_w = (const __nv_bfloat16*)d_in[9];
    p.out = (__nv_bfloat16*)d_out;
    p.scr = scr;
    fused_decode_kernel<<<NCTA, NTHREADS, SMEM_BYTES, cudaStreamPerThread>>>(p);
}
```
